```python
import torch

def _softmax(x, axis=-1):
    return torch.softmax(x, dim=axis)
def _gelu(x):
    return torch.nn.functional.gelu(x, approximate="tanh")
def _silu(x):
    return torch.nn.functional.silu(x)
def _sigmoid(x):
    return torch.sigmoid(x)
def _layernorm(x, axis=-1, eps=1e-5):
    m = x.mean(dim=axis, keepdim=True)
    v = x.var(dim=axis, keepdim=True, unbiased=False)
    return (x - m) / torch.sqrt(v + eps)
def _scatter_add(tgt, idx, src, axis=0):
    return tgt.clone().index_add_(axis, idx, src)
def _segment_sum(src, seg, n):
    out = torch.zeros((n,) + src.shape[1:], dtype=src.dtype)
    return out.index_add_(0, seg, src)
def _pad(x, pw):
    flat = tuple(v for pair in reversed(pw) for v in pair)
    return torch.nn.functional.pad(x, flat)

kernel_name = 'gated_mix__ssm_conv_s4__linear_attn_block__prompt'

def setup_inputs():

    _w = (lambda a: (lambda t: t.to(torch.bfloat16) if t.is_floating_point() else t)(torch.as_tensor(a)))
    def _A_setup():
        B, L, D, N = 1, 2048, 640, 192
        A_re = -(lambda _x: torch.exp(torch.as_tensor(_x)))((lambda *s: torch.randn(*s, dtype=torch.bfloat16) * 6.4)(D, N))
        A_im = torch.pi * (lambda *s: torch.randn(*s, dtype=torch.bfloat16) * 0.05)(D, N)
        B_re = (lambda *s: torch.randn(*s, dtype=torch.bfloat16) * 0.1)(D, N)
        B_im = (lambda *s: torch.randn(*s, dtype=torch.bfloat16) * 0.1)(D, N)
        C_re = (lambda *s: torch.randn(*s, dtype=torch.bfloat16) * 0.1)(D, N)
        C_im = (lambda *s: torch.randn(*s, dtype=torch.bfloat16) * 0.1)(D, N)
        log_dt = (lambda *s: torch.randn(*s, dtype=torch.bfloat16) * 0.05)(D) * 0.5 - 4.0
        Dskip = (lambda *s: torch.randn(*s, dtype=torch.bfloat16) * 0.05)(D)
        return {
            "u": _w((lambda *s: torch.randn(*s, dtype=torch.bfloat16) * 0.05)(B, L, D)),
            "A_re": _w(A_re),
            "A_im": _w(A_im),
            "B_re": _w(B_re),
            "B_im": _w(B_im),
            "C_re": _w(C_re),
            "C_im": _w(C_im),
            "log_dt": _w(log_dt),
            "Dskip": _w(Dskip),
        }
    _A_in = _A_setup()

    def _B_setup():
        B, S, D = 1, 2048, 640
        return {
            "x": _w((lambda *s: torch.randn(*s, dtype=torch.bfloat16) * 0.05)(B, S, D)),
            "wqkv": _w((lambda *s: torch.randn(*s, dtype=torch.bfloat16) * 0.4)(D, 3 * D)),
            "wo": _w((lambda *s: torch.randn(*s, dtype=torch.bfloat16) * 0.05)(D, D)),
        }
    _B_in = _B_setup()

    return {
        "A_u": _A_in["u"],
        "A_A_re": _A_in["A_re"],
        "A_A_im": _A_in["A_im"],
        "A_B_re": _A_in["B_re"],
        "A_B_im": _A_in["B_im"],
        "A_C_re": _A_in["C_re"],
        "A_C_im": _A_in["C_im"],
        "A_log_dt": _A_in["log_dt"],
        "A_Dskip": _A_in["Dskip"],
        "B_x": _B_in["x"],
        "B_wqkv": _B_in["wqkv"],
        "B_wo": _B_in["wo"],
        "gate_w": _w((lambda *s: torch.randn(*s, dtype=torch.bfloat16) * 0.05)(640) * 16.0),
    }

def reference(A_u, A_A_re, A_A_im, A_B_re, A_B_im, A_C_re, A_C_im, A_log_dt, A_Dskip, B_x, B_wqkv, B_wo, gate_w):
    def _A_ref(u, A_re, A_im, B_re, B_im, C_re, C_im, log_dt, Dskip):
        Bsz, L, D = u.shape
        dt = torch.exp(log_dt)[:, None]
        A = A_re + 1j * A_im
        Bc = B_re + 1j * B_im
        Cc = C_re + 1j * C_im
        logdA = dt * A
        dB = dt * Bc
        l = (lambda x, dt: x.to(dt))(torch.arange(L), A_re.dtype)
        P = torch.exp(logdA[:, :, None] * l[None, None, :])
        K = torch.einsum("dn,dnl,dn->dl", Cc, P, dB).real
        L2 = 2 * L
        Kp = _pad(K, ((0, 0), (0, L)))
        up = (lambda x, *d: x.permute(*d))(u, 0, 2, 1)
        up = _pad(up, ((0, 0), (0, 0), (0, L)))
        Kf = (lambda x, axes=(-2,-1): torch.fft.rfft2(x.float(), dim=axes))(Kp[:, None, :], axes=(-2, -1))
        Uf = (lambda x, axes=(-2,-1): torch.fft.rfft2(x.float(), dim=axes))(up[:, :, None, :], axes=(-2, -1))
        Yf = Uf * Kf[None, :, :, :]
        y = (lambda x, s, axes=(-2,-1): torch.fft.irfft2(x, s=s, dim=axes).to(torch.bfloat16))(Yf, (1, L2), axes=(-2, -1))[:, :, 0, :L]
        y = (lambda x, *d: x.permute(*d))(y, 0, 2, 1) + u * Dskip[None, None, :]
        return y

    def _B_ref(x, wqkv, wo):
        B, S, D = x.shape
        H = 32; Dh = D // H
        qkv = (lambda x, *d: x.permute(*d))((x @ wqkv).reshape(B, S, 3, H, Dh), 2, 0, 3, 1, 4)
        q, k, v = qkv[0], qkv[1], qkv[2]
        phi = lambda t: torch.where(t > 0, t + 1, torch.exp(t)) + 1e-6
        pq, pk = phi(q), phi(k)
        kv = torch.einsum("bhsd,bhse->bhde", pk, v)
        z = torch.einsum("bhsd->bhd", pk)
        num = torch.einsum("bhqd,bhde->bhqe", pq, kv)
        den = torch.einsum("bhqd,bhd->bhq", pq, z)[..., None] + 1e-6
        o = num / den
        return (lambda x, *d: x.permute(*d))(o, 0, 2, 1, 3).reshape(B, S, D) @ wo

    x = A_u
    g = _sigmoid((x * gate_w).sum(-1, keepdims=True))
    a = _A_ref(x, A_A_re, A_A_im, A_B_re, A_B_im, A_C_re, A_C_im, A_log_dt, A_Dskip)
    b = _B_ref(x, B_wqkv, B_wo)
    return g * a + (1 - g) * b
```

```cpp
#include <cuda_runtime.h>
#include <cuda_bf16.h>
#include <cuda.h>
#include <cudaTypedefs.h>
#include <stdint.h>

typedef __nv_bfloat16 bf16;

namespace {

constexpr uint32_t SB = 1024, STG = 47104;
constexpr uint32_t A_WO = SB, WOP = 12800, A_K = SB + 51200, A_V = SB + 71680, A_Q = SB + 102400, A_B88 = A_Q;
constexpr uint32_t A_U = SB + 3 * STG, UP = 5632, A_BAR = A_U + 5 * UP, A_DUM = A_BAR + 256, A_TAB = A_DUM + 256, TABP = 5568;
constexpr uint32_t PG = 3, A_PA = A_U + 57344, A_PART = A_PA + PG * 4096, A_GW = A_PART + 16384, SMEM_BYTES = A_GW - SB + 1408;
constexpr uint32_t A_PH = A_TAB + 4 * TABP, A_P4 = A_TAB + 44288, A_XT = A_PA, A_O1 = SB + 122880, A_O2 = A_TAB, A_PB = SB + 122880, A_EM = A_P4 + 4 * 2560, A_TAG = A_BAR + 128;
static_assert(A_O1 + 40960 <= A_BAR && A_O2 + 40960 <= A_PART, "landing zones");
static_assert(A_EM + 2560 <= A_GW && A_TAB + 5 * TABP <= A_PA && SMEM_BYTES <= 232448, "shared-memory map");
constexpr uint32_t B_EMPTY = A_BAR, B_W1D = A_BAR + 24, B_C2 = A_BAR + 32, B_UT = A_BAR + 40, B_DONE = A_BAR + 48,
                   B_TB = A_BAR + 56, B_AT = A_BAR + 64, B_TF = A_BAR + 72,
                   B_U = A_BAR + 80, B_WO = A_BAR + 88, B_FULL = A_BAR + 104, B_XS = A_BAR + 136, B_G = A_BAR + 144, B_C1 = A_BAR + 152;

struct __align__(64) Params {
  const bf16 *Are, *Aim, *Bre, *Bim, *Cre, *Cim, *logdt, *dskip, *gatew, *x;
  CUtensorMap mx, mw64, mw16, mwo, mout, mxs, mut;
};

struct __align__(1024) Scratch {
  char uT[640 * UP];
  char aT[640 * 4096];
  char o[128 * 20480];
  char kv[128 * 3840];
  unsigned cnt[32];
};
__device__ Scratch g_s;
#define TS(i) do { } while (0)

#define SPIN_GUARD(c)
__device__ __forceinline__ uint64_t desc(uint32_t lo, uint32_t hi) { uint64_t d; asm("mov.b64 %0, {%1,%2};" : "=l"(d) : "r"(lo), "r"(hi)); return d; }
__device__ constexpr uint32_t dlo(uint32_t addr, uint32_t lbo) { return (addr >> 4) | ((lbo >> 4) << 16); }
__device__ constexpr uint32_t dhi(uint32_t sbo, uint32_t swz) { return (sbo >> 4) | (swz << 30); }
__device__ __forceinline__ bool elect() { uint32_t r; asm volatile("{\n.reg .pred p;\nelect.sync _|p, 0xffffffff;\nselp.u32 %0, 1, 0, p;\n}" : "=r"(r)); return r; }
__device__ __forceinline__ void mbar_init(uint32_t b, uint32_t c) { asm volatile("mbarrier.init.shared::cta.b64 [%0], %1;" ::"r"(b), "r"(c) : "memory"); }
__device__ __forceinline__ void mbar_expect(uint32_t b, uint32_t bytes) { asm volatile("mbarrier.arrive.expect_tx.shared::cta.b64 _, [%0], %1;" ::"r"(b), "r"(bytes) : "memory"); }
__device__ __forceinline__ void mbar_arrive(uint32_t b) { asm volatile("mbarrier.arrive.shared::cta.b64 _, [%0];" ::"r"(b) : "memory"); }
__device__ __forceinline__ void mbar_wait_b(uint32_t b, uint32_t par, uint32_t lim) {
  asm volatile("{\n.reg .pred p;\n.reg .u32 c;\nmov.u32 c, 0;\nWL%=:\nmbarrier.try_wait.parity.shared::cta.b64 p, [%0], %1;\n@p bra WD%=;\n"
               "add.u32 c, c, 1;\nsetp.lt.u32 p, c, %2;\n@p bra WL%=;\ntrap;\nWD%=:\n}" ::"r"(b), "r"(par), "r"(lim) : "memory");
}
__device__ __forceinline__ void mbar_wait(uint32_t b, uint32_t par) {
  asm volatile("{\n.reg .pred p;\nWL%=:\nmbarrier.try_wait.parity.shared::cta.b64 p, [%0], %1;\n@!p bra WL%=;\n}" ::"r"(b), "r"(par) : "memory");
}
__device__ __forceinline__ void tma2(uint32_t dst, const CUtensorMap* m, uint32_t bar, int c0, int c1) {
  asm volatile("cp.async.bulk.tensor.2d.shared::cluster.global.mbarrier::complete_tx::bytes [%0], [%1, {%3,%4}], [%2];" ::"r"(dst), "l"(m), "r"(bar), "r"(c0), "r"(c1) : "memory");
}
__device__ __forceinline__ void tma3(uint32_t dst, const CUtensorMap* m, uint32_t bar, int c0, int c1, int c2) {
  asm volatile("cp.async.bulk.tensor.3d.shared::cluster.global.mbarrier::complete_tx::bytes [%0], [%1, {%3,%4,%5}], [%2];" ::"r"(dst), "l"(m), "r"(bar), "r"(c0), "r"(c1), "r"(c2) : "memory");
}
__device__ __forceinline__ void tma2_store(const CUtensorMap* m, uint32_t src, int c0, int c1) {
  asm volatile("cp.async.bulk.tensor.2d.global.shared::cta.bulk_group [%0, {%2,%3}], [%1];" ::"l"(m), "r"(src), "r"(c0), "r"(c1) : "memory");
}
__device__ __forceinline__ void bulk_s2g(void* dst, uint32_t src, uint32_t bytes) {
  asm volatile("cp.async.bulk.global.shared::cta.bulk_group [%0], [%1], %2;" ::"l"(dst), "r"(src), "r"(bytes) : "memory");
}
__device__ __forceinline__ void bulk_g2s(uint32_t dst, const void* src, uint32_t bytes, uint32_t bar) {
  asm volatile("cp.async.bulk.shared::cluster.global.mbarrier::complete_tx::bytes [%0], [%1], %2, [%3];" ::"r"(dst), "l"(src), "r"(bytes), "r"(bar) : "memory");
}
__device__ __forceinline__ void bulk_commit() { asm volatile("cp.async.bulk.commit_group;" ::: "memory"); }
__device__ __forceinline__ void bulk_wait_read() { asm volatile("cp.async.bulk.wait_group.read 0;" ::: "memory"); }
__device__ __forceinline__ void wg_fence() { asm volatile("wgmma.fence.sync.aligned;" ::: "memory"); }
__device__ __forceinline__ void wg_commit() { asm volatile("wgmma.commit_group.sync.aligned;" ::: "memory"); }
template <int N> __device__ __forceinline__ void wg_wait() { asm volatile("wgmma.wait_group.sync.aligned %0;" ::"n"(N) : "memory"); }
__device__ __forceinline__ void ldsm4t(uint32_t (&r)[4], uint32_t a) {
  asm volatile("ldmatrix.sync.aligned.m8n8.x4.trans.shared.b16 {%0,%1,%2,%3},[%4];" : "=r"(r[0]), "=r"(r[1]), "=r"(r[2]), "=r"(r[3]) : "r"(a) : "memory");
}
__device__ __forceinline__ void ldsm4(uint32_t (&r)[4], uint32_t a) {
  asm volatile("ldmatrix.sync.aligned.m8n8.x4.shared.b16 {%0,%1,%2,%3},[%4];" : "=r"(r[0]), "=r"(r[1]), "=r"(r[2]), "=r"(r[3]) : "r"(a) : "memory");
}
__device__ __forceinline__ void stsm4(uint32_t a, uint32_t r0, uint32_t r1, uint32_t r2, uint32_t r3) {
  asm volatile("stmatrix.sync.aligned.m8n8.x4.shared.b16 [%0], {%1,%2,%3,%4};" ::"r"(a), "r"(r0), "r"(r1), "r"(r2), "r"(r3) : "memory");
}
__device__ __forceinline__ void stsm2(uint32_t a, uint32_t r0, uint32_t r1) {
  asm volatile("stmatrix.sync.aligned.m8n8.x2.shared.b16 [%0], {%1,%2};" ::"r"(a), "r"(r0), "r"(r1) : "memory");
}
__device__ __forceinline__ void stsm4t(uint32_t a, uint32_t r0, uint32_t r1, uint32_t r2, uint32_t r3) {
  asm volatile("stmatrix.sync.aligned.m8n8.x4.trans.shared.b16 [%0], {%1,%2,%3,%4};" ::"r"(a), "r"(r0), "r"(r1), "r"(r2), "r"(r3) : "memory");
}
__device__ __forceinline__ void mma(float* c, const uint32_t (&a)[4], uint32_t b0, uint32_t b1) {
  asm volatile("mma.sync.aligned.m16n8k16.row.col.f32.bf16.bf16.f32 {%0,%1,%2,%3},{%4,%5,%6,%7},{%8,%9},{%0,%1,%2,%3};"
               : "+f"(c[0]), "+f"(c[1]), "+f"(c[2]), "+f"(c[3]) : "r"(a[0]), "r"(a[1]), "r"(a[2]), "r"(a[3]), "r"(b0), "r"(b1));
}
__device__ __forceinline__ uint32_t pack2(float lo, float hi) { uint32_t r; asm("cvt.rn.bf16x2.f32 %0, %1, %2;" : "=r"(r) : "f"(hi), "f"(lo)); return r; }
__device__ __forceinline__ float bflo(uint32_t v) { return __uint_as_float(v << 16); }
__device__ __forceinline__ float bfhi(uint32_t v) { return __uint_as_float(v & 0xFFFF0000u); }
__device__ __forceinline__ uint32_t hadd2(uint32_t a, uint32_t b) { uint32_t r; asm("add.rn.bf16x2 %0, %1, %2;" : "=r"(r) : "r"(a), "r"(b)); return r; }
__device__ __forceinline__ void sts128(uint32_t a, uint32_t x, uint32_t y, uint32_t z, uint32_t w) { asm volatile("st.shared.v4.b32 [%0], {%1,%2,%3,%4};" ::"r"(a), "r"(x), "r"(y), "r"(z), "r"(w) : "memory"); }
__device__ __forceinline__ void sts128f(uint32_t a, const float* v) { asm volatile("st.shared.v4.f32 [%0], {%1,%2,%3,%4};" ::"r"(a), "f"(v[0]), "f"(v[1]), "f"(v[2]), "f"(v[3]) : "memory"); }
__device__ __forceinline__ void lds128f(float* v, uint32_t a) { asm volatile("ld.shared.v4.f32 {%0,%1,%2,%3}, [%4];" : "=f"(v[0]), "=f"(v[1]), "=f"(v[2]), "=f"(v[3]) : "r"(a) : "memory"); }
__device__ __forceinline__ void sts64(uint32_t a, uint32_t x, uint32_t y) { asm volatile("st.shared.v2.b32 [%0], {%1,%2};" ::"r"(a), "r"(x), "r"(y) : "memory"); }
__device__ __forceinline__ void lds64f(float& x, float& y, uint32_t a) { asm volatile("ld.shared.v2.f32 {%0,%1}, [%2];" : "=f"(x), "=f"(y) : "r"(a) : "memory"); }
__device__ __forceinline__ void ldg64nc(uint32_t& x, uint32_t& y, const void* p) { asm volatile("ld.global.nc.v2.b32 {%0,%1}, [%2];" : "=r"(x), "=r"(y) : "l"(p)); }
__device__ __forceinline__ void sts32(uint32_t a, uint32_t x) { asm volatile("st.shared.b32 [%0], %1;" ::"r"(a), "r"(x) : "memory"); }
__device__ __forceinline__ void sts16(uint32_t a, uint32_t x) { asm volatile("st.shared.b16 [%0], %1;" ::"r"(a), "h"((uint16_t)x) : "memory"); }
__device__ __forceinline__ uint4 lds128(uint32_t a) { uint4 v; asm volatile("ld.shared.v4.b32 {%0,%1,%2,%3}, [%4];" : "=r"(v.x), "=r"(v.y), "=r"(v.z), "=r"(v.w) : "r"(a) : "memory"); return v; }
__device__ __forceinline__ uint32_t lds32(uint32_t a) { uint32_t v; asm volatile("ld.shared.b32 %0, [%1];" : "=r"(v) : "r"(a) : "memory"); return v; }
__device__ __forceinline__ float lds32f(uint32_t a) { return __uint_as_float(lds32(a)); }
__device__ __forceinline__ void ldg128nc(uint32_t (&v)[4], const void* p) { asm volatile("ld.global.nc.v4.b32 {%0,%1,%2,%3}, [%4];" : "=r"(v[0]), "=r"(v[1]), "=r"(v[2]), "=r"(v[3]) : "l"(p)); }
__device__ __forceinline__ void stg128(void* p, uint32_t x, uint32_t y, uint32_t z, uint32_t w) { asm volatile("st.global.v4.b32 [%0], {%1,%2,%3,%4};" ::"l"(p), "r"(x), "r"(y), "r"(z), "r"(w) : "memory"); }
__device__ __forceinline__ uint32_t ldg16(const void* p) { uint16_t v; asm volatile("ld.global.nc.u16 %0, [%1];" : "=h"(v) : "l"(p)); return (uint32_t)v; }
__device__ __forceinline__ uint32_t ldg32(const void* p) { uint32_t v; asm volatile("ld.global.nc.b32 %0, [%1];" : "=r"(v) : "l"(p)); return v; }
__device__ __forceinline__ void prefetch(const void* p) { asm volatile("prefetch.global.L2 [%0];" ::"l"(p)); }
__device__ __forceinline__ void bar_sync(int id, int n) { asm volatile("bar.sync %0, %1;" ::"r"(id), "r"(n) : "memory"); }
__device__ __forceinline__ void fence_async_g() { asm volatile("fence.proxy.async.global;" ::: "memory"); }
__device__ __forceinline__ void fence_async_s() { asm volatile("fence.proxy.async.shared::cta;" ::: "memory"); }
__device__ __forceinline__ void bar_arrive(int id, int n) { asm volatile("bar.arrive %0, %1;" ::"r"(id), "r"(n) : "memory"); }
__device__ __forceinline__ void flag_wait(unsigned target) {
  asm volatile("{\n.reg .pred p;\n.reg .u32 c, v;\nmov.u32 c, 0;\nFL%=:\nld.acquire.gpu.global.u32 v, [%0];\nsub.u32 v, v, %1;\nsetp.ge.s32 p, v, 0;\n@p bra FD%=;\n"
               "add.u32 c, c, 1;\nsetp.lt.u32 p, c, 1000000;\n@p bra FL%=;\ntrap;\nFD%=:\n}" ::"l"(g_s.cnt), "r"(target) : "memory");
}
__device__ __forceinline__ void ld_unit(uint32_t (&v)[4], const void* p) {
  asm volatile("{\n.reg .b128 q;\n.reg .b64 a, b;\nld.relaxed.gpu.global.b128 q, [%4];\nmov.b128 {a, b}, q;\nmov.b64 {%0,%1}, a;\nmov.b64 {%2,%3}, b;\n}"
               : "=r"(v[0]), "=r"(v[1]), "=r"(v[2]), "=r"(v[3]) : "l"(p) : "memory");
}
__device__ __forceinline__ void re_unit(uint32_t (&v)[4], const void* p, uint32_t old) {
  if ((v[0] & 1) == old) ld_unit(v, p);
}
__device__ __forceinline__ void poll_tag(const void* p, uint32_t old) {
  int spin = 0; (void)spin;
  for (;;) {
    uint32_t v;
    asm volatile("ld.relaxed.gpu.global.b32 %0, [%1];" : "=r"(v) : "l"(p) : "memory");
    if (__all_sync(0xffffffffu, (v ^ old) & 1)) break;
    SPIN_GUARD(spin)
  }
}
#define GU 2
#define FULLI
#define INITM 7
#define KSP 3
#define GP 3
#define UBX 20
#define USL 200
#define WSL 500
#define C1P 1
#define TFC 3
#define EARLY 2
#define NSPLIT 1
#define KSLEEP 50
#define NSLEEP 100
__device__ __forceinline__ void st_unit(void* p, uint32_t x, uint32_t y, uint32_t z, uint32_t w) {
  asm volatile("{\n.reg .b128 q;\n.reg .b64 a, b;\nmov.b64 a, {%1,%2};\nmov.b64 b, {%3,%4};\nmov.b128 q, {a, b};\nst.relaxed.gpu.global.b128 [%0], q;\n}"
               ::"l"(p), "r"(x), "r"(y), "r"(z), "r"(w) : "memory");
}
__device__ __forceinline__ void pool(uint32_t u0, uint32_t u1, uint32_t da) {
  float s[32];
#pragma unroll
  for (int i = 0; i < 4; i++) {
    const uint4 v = lds128(((i & 1) ? u1 : u0) + (i >> 1) * 16);
    s[8 * i] = bflo(v.x); s[8 * i + 1] = bfhi(v.x); s[8 * i + 2] = bflo(v.y); s[8 * i + 3] = bfhi(v.y);
    s[8 * i + 4] = bflo(v.z); s[8 * i + 5] = bfhi(v.z); s[8 * i + 6] = bflo(v.w); s[8 * i + 7] = bfhi(v.w);
  }
  s[3] = 0.f;
#pragma unroll
  for (int i = 5; i <= 26; i++) s[i] += s[i - 1];
  uint32_t w7[4], w9[4];
#pragma unroll
  for (int r = 0; r < 4; r++) {
    w7[r] = pack2(s[2 * r + 19] - s[2 * r + 12], s[2 * r + 20] - s[2 * r + 13]);
    w9[r] = pack2(s[2 * r + 12] - s[2 * r + 3], s[2 * r + 13] - s[2 * r + 4]);
  }
  sts128(da, w7[0], w7[1], w7[2], w7[3]);
  sts128(da + 2048, w9[0], w9[1], w9[2], w9[3]);
}
__device__ __forceinline__ uint32_t tagged(uint32_t x, uint32_t old) { return (x | 1u) ^ old; }
template <int N> __device__ __forceinline__ void pin(float (&d)[N]) {
#pragma unroll
  for (int i = 0; i < N; i++) asm volatile("" : "+f"(d[i])::"memory");
}
__device__ __forceinline__ uint32_t movm(uint32_t a) { uint32_t d; asm volatile("movmatrix.sync.aligned.m8n8.trans.b16 %0, %1;" : "=r"(d) : "r"(a)); return d; }
__device__ __forceinline__ float ex2f(float x) { float r; asm("ex2.approx.ftz.f32 %0, %1;" : "=f"(r) : "f"(x)); return r; }
__device__ __forceinline__ float rcpf(float x) { float r; asm("rcp.approx.ftz.f32 %0, %1;" : "=f"(r) : "f"(x)); return r; }
__device__ __forceinline__ uint32_t phi2(uint32_t t, uint32_t zero) {
  uint32_t n, m;
  asm("min.bf16x2 %0, %1, %2;" : "=r"(n) : "r"(t), "r"(zero));
  asm("max.bf16x2 %0, %1, %2;" : "=r"(m) : "r"(t), "r"(0x35863586u));
  return hadd2(m, pack2(ex2f(bflo(n) * 1.4426950408889634f), ex2f(bfhi(n) * 1.4426950408889634f)));
}

__device__ __forceinline__ void wgmma_rs_n192(float (&d)[124], uint32_t a0, uint32_t a1, uint32_t a2, uint32_t a3, uint64_t db, int sc){
  asm volatile("{\n.reg .pred p;\nsetp.ne.b32 p, %101, 0;\nwgmma.mma_async.sync.aligned.m64n192k16.f32.bf16.bf16 {%0,%1,%2,%3,%4,%5,%6,%7,%8,%9,%10,%11,%12,%13,%14,%15,%16,%17,%18,%19,%20,%21,%22,%23,%24,%25,%26,%27,%28,%29,%30,%31,%32,%33,%34,%35,%36,%37,%38,%39,%40,%41,%42,%43,%44,%45,%46,%47,%48,%49,%50,%51,%52,%53,%54,%55,%56,%57,%58,%59,%60,%61,%62,%63,%64,%65,%66,%67,%68,%69,%70,%71,%72,%73,%74,%75,%76,%77,%78,%79,%80,%81,%82,%83,%84,%85,%86,%87,%88,%89,%90,%91,%92,%93,%94,%95}, {%96,%97,%98,%99}, %100, p, 1, 1, 1;\n}\n" : "+f"(d[0]),"+f"(d[1]),"+f"(d[2]),"+f"(d[3]),"+f"(d[4]),"+f"(d[5]),"+f"(d[6]),"+f"(d[7]),"+f"(d[8]),"+f"(d[9]),"+f"(d[10]),"+f"(d[11]),"+f"(d[12]),"+f"(d[13]),"+f"(d[14]),"+f"(d[15]),"+f"(d[16]),"+f"(d[17]),"+f"(d[18]),"+f"(d[19]),"+f"(d[20]),"+f"(d[21]),"+f"(d[22]),"+f"(d[23]),"+f"(d[24]),"+f"(d[25]),"+f"(d[26]),"+f"(d[27]),"+f"(d[28]),"+f"(d[29]),"+f"(d[30]),"+f"(d[31]),"+f"(d[32]),"+f"(d[33]),"+f"(d[34]),"+f"(d[35]),"+f"(d[36]),"+f"(d[37]),"+f"(d[38]),"+f"(d[39]),"+f"(d[40]),"+f"(d[41]),"+f"(d[42]),"+f"(d[43]),"+f"(d[44]),"+f"(d[45]),"+f"(d[46]),"+f"(d[47]),"+f"(d[48]),"+f"(d[49]),"+f"(d[50]),"+f"(d[51]),"+f"(d[52]),"+f"(d[53]),"+f"(d[54]),"+f"(d[55]),"+f"(d[56]),"+f"(d[57]),"+f"(d[58]),"+f"(d[59]),"+f"(d[60]),"+f"(d[61]),"+f"(d[62]),"+f"(d[63]),"+f"(d[64]),"+f"(d[65]),"+f"(d[66]),"+f"(d[67]),"+f"(d[68]),"+f"(d[69]),"+f"(d[70]),"+f"(d[71]),"+f"(d[72]),"+f"(d[73]),"+f"(d[74]),"+f"(d[75]),"+f"(d[76]),"+f"(d[77]),"+f"(d[78]),"+f"(d[79]),"+f"(d[80]),"+f"(d[81]),"+f"(d[82]),"+f"(d[83]),"+f"(d[84]),"+f"(d[85]),"+f"(d[86]),"+f"(d[87]),"+f"(d[88]),"+f"(d[89]),"+f"(d[90]),"+f"(d[91]),"+f"(d[92]),"+f"(d[93]),"+f"(d[94]),"+f"(d[95]) : "r"(a0), "r"(a1), "r"(a2), "r"(a3), "l"(db), "r"(sc));
}
__device__ __forceinline__ void wgmma_rs_n48t(float (&d)[124], uint32_t a0, uint32_t a1, uint32_t a2, uint32_t a3, uint64_t db, int sc){
  asm volatile("{\n.reg .pred p;\nsetp.ne.b32 p, %29, 0;\nwgmma.mma_async.sync.aligned.m64n48k16.f32.bf16.bf16 {%0,%1,%2,%3,%4,%5,%6,%7,%8,%9,%10,%11,%12,%13,%14,%15,%16,%17,%18,%19,%20,%21,%22,%23}, {%24,%25,%26,%27}, %28, p, 1, 1, 1;\n}\n" : "+f"(d[96]),"+f"(d[97]),"+f"(d[98]),"+f"(d[99]),"+f"(d[100]),"+f"(d[101]),"+f"(d[102]),"+f"(d[103]),"+f"(d[104]),"+f"(d[105]),"+f"(d[106]),"+f"(d[107]),"+f"(d[108]),"+f"(d[109]),"+f"(d[110]),"+f"(d[111]),"+f"(d[112]),"+f"(d[113]),"+f"(d[114]),"+f"(d[115]),"+f"(d[116]),"+f"(d[117]),"+f"(d[118]),"+f"(d[119]) : "r"(a0), "r"(a1), "r"(a2), "r"(a3), "l"(db), "r"(sc));
}
__device__ __forceinline__ void wgmma_rs_n8(float (&d)[124], uint32_t a0, uint32_t a1, uint32_t a2, uint32_t a3, uint64_t db, int sc){
  asm volatile("{\n.reg .pred p;\nsetp.ne.b32 p, %9, 0;\nwgmma.mma_async.sync.aligned.m64n8k16.f32.bf16.bf16 {%0,%1,%2,%3}, {%4,%5,%6,%7}, %8, p, 1, 1, 0;\n}\n" : "+f"(d[120]),"+f"(d[121]),"+f"(d[122]),"+f"(d[123]) : "r"(a0), "r"(a1), "r"(a2), "r"(a3), "l"(db), "r"(sc));
}
__device__ __forceinline__ void wgmma_rs_n64a(float (&d)[124], uint32_t a0, uint32_t a1, uint32_t a2, uint32_t a3, uint64_t db, int sc){
  asm volatile("{\n.reg .pred p;\nsetp.ne.b32 p, %37, 0;\nwgmma.mma_async.sync.aligned.m64n64k16.f32.bf16.bf16 {%0,%1,%2,%3,%4,%5,%6,%7,%8,%9,%10,%11,%12,%13,%14,%15,%16,%17,%18,%19,%20,%21,%22,%23,%24,%25,%26,%27,%28,%29,%30,%31}, {%32,%33,%34,%35}, %36, p, 1, 1, 1;\n}\n" : "+f"(d[0]),"+f"(d[1]),"+f"(d[2]),"+f"(d[3]),"+f"(d[4]),"+f"(d[5]),"+f"(d[6]),"+f"(d[7]),"+f"(d[8]),"+f"(d[9]),"+f"(d[10]),"+f"(d[11]),"+f"(d[12]),"+f"(d[13]),"+f"(d[14]),"+f"(d[15]),"+f"(d[16]),"+f"(d[17]),"+f"(d[18]),"+f"(d[19]),"+f"(d[20]),"+f"(d[21]),"+f"(d[22]),"+f"(d[23]),"+f"(d[24]),"+f"(d[25]),"+f"(d[26]),"+f"(d[27]),"+f"(d[28]),"+f"(d[29]),"+f"(d[30]),"+f"(d[31]) : "r"(a0), "r"(a1), "r"(a2), "r"(a3), "l"(db), "r"(sc));
}
__device__ __forceinline__ void wgmma_rs_n64b(float (&d)[124], uint32_t a0, uint32_t a1, uint32_t a2, uint32_t a3, uint64_t db, int sc){
  asm volatile("{\n.reg .pred p;\nsetp.ne.b32 p, %37, 0;\nwgmma.mma_async.sync.aligned.m64n64k16.f32.bf16.bf16 {%0,%1,%2,%3,%4,%5,%6,%7,%8,%9,%10,%11,%12,%13,%14,%15,%16,%17,%18,%19,%20,%21,%22,%23,%24,%25,%26,%27,%28,%29,%30,%31}, {%32,%33,%34,%35}, %36, p, 1, 1, 1;\n}\n" : "+f"(d[32]),"+f"(d[33]),"+f"(d[34]),"+f"(d[35]),"+f"(d[36]),"+f"(d[37]),"+f"(d[38]),"+f"(d[39]),"+f"(d[40]),"+f"(d[41]),"+f"(d[42]),"+f"(d[43]),"+f"(d[44]),"+f"(d[45]),"+f"(d[46]),"+f"(d[47]),"+f"(d[48]),"+f"(d[49]),"+f"(d[50]),"+f"(d[51]),"+f"(d[52]),"+f"(d[53]),"+f"(d[54]),"+f"(d[55]),"+f"(d[56]),"+f"(d[57]),"+f"(d[58]),"+f"(d[59]),"+f"(d[60]),"+f"(d[61]),"+f"(d[62]),"+f"(d[63]) : "r"(a0), "r"(a1), "r"(a2), "r"(a3), "l"(db), "r"(sc));
}
__device__ __forceinline__ void wgmma_rs_n64c(float (&d)[124], uint32_t a0, uint32_t a1, uint32_t a2, uint32_t a3, uint64_t db, int sc){
  asm volatile("{\n.reg .pred p;\nsetp.ne.b32 p, %37, 0;\nwgmma.mma_async.sync.aligned.m64n64k16.f32.bf16.bf16 {%0,%1,%2,%3,%4,%5,%6,%7,%8,%9,%10,%11,%12,%13,%14,%15,%16,%17,%18,%19,%20,%21,%22,%23,%24,%25,%26,%27,%28,%29,%30,%31}, {%32,%33,%34,%35}, %36, p, 1, 1, 1;\n}\n" : "+f"(d[64]),"+f"(d[65]),"+f"(d[66]),"+f"(d[67]),"+f"(d[68]),"+f"(d[69]),"+f"(d[70]),"+f"(d[71]),"+f"(d[72]),"+f"(d[73]),"+f"(d[74]),"+f"(d[75]),"+f"(d[76]),"+f"(d[77]),"+f"(d[78]),"+f"(d[79]),"+f"(d[80]),"+f"(d[81]),"+f"(d[82]),"+f"(d[83]),"+f"(d[84]),"+f"(d[85]),"+f"(d[86]),"+f"(d[87]),"+f"(d[88]),"+f"(d[89]),"+f"(d[90]),"+f"(d[91]),"+f"(d[92]),"+f"(d[93]),"+f"(d[94]),"+f"(d[95]) : "r"(a0), "r"(a1), "r"(a2), "r"(a3), "l"(db), "r"(sc));
}
__device__ __forceinline__ void wgmma_ss_n48(float (&d)[24], uint64_t da, uint64_t db, int sc){
  asm volatile("{\n.reg .pred p;\nsetp.ne.b32 p, %26, 0;\nwgmma.mma_async.sync.aligned.m64n48k16.f32.bf16.bf16 {%0,%1,%2,%3,%4,%5,%6,%7,%8,%9,%10,%11,%12,%13,%14,%15,%16,%17,%18,%19,%20,%21,%22,%23}, %24, %25, p, 1, 1, 1, 1;\n}\n" : "+f"(d[0]),"+f"(d[1]),"+f"(d[2]),"+f"(d[3]),"+f"(d[4]),"+f"(d[5]),"+f"(d[6]),"+f"(d[7]),"+f"(d[8]),"+f"(d[9]),"+f"(d[10]),"+f"(d[11]),"+f"(d[12]),"+f"(d[13]),"+f"(d[14]),"+f"(d[15]),"+f"(d[16]),"+f"(d[17]),"+f"(d[18]),"+f"(d[19]),"+f"(d[20]),"+f"(d[21]),"+f"(d[22]),"+f"(d[23]) : "l"(da), "l"(db), "r"(sc));
}
__device__ __forceinline__ void wgmma_ss_n40(float (&d)[20], uint64_t da, uint64_t db, int sc){
  asm volatile("{\n.reg .pred p;\nsetp.ne.b32 p, %22, 0;\nwgmma.mma_async.sync.aligned.m64n40k16.f32.bf16.bf16 {%0,%1,%2,%3,%4,%5,%6,%7,%8,%9,%10,%11,%12,%13,%14,%15,%16,%17,%18,%19}, %20, %21, p, 1, 1, 1, 1;\n}\n" : "+f"(d[0]),"+f"(d[1]),"+f"(d[2]),"+f"(d[3]),"+f"(d[4]),"+f"(d[5]),"+f"(d[6]),"+f"(d[7]),"+f"(d[8]),"+f"(d[9]),"+f"(d[10]),"+f"(d[11]),"+f"(d[12]),"+f"(d[13]),"+f"(d[14]),"+f"(d[15]),"+f"(d[16]),"+f"(d[17]),"+f"(d[18]),"+f"(d[19]) : "l"(da), "l"(db), "r"(sc));
}
__device__ __forceinline__ void wgmma_rs_n88(float (&d)[44], uint32_t a0, uint32_t a1, uint32_t a2, uint32_t a3, uint64_t db, int sc){
  asm volatile("{\n.reg .pred p;\nsetp.ne.b32 p, %49, 0;\nwgmma.mma_async.sync.aligned.m64n88k16.f32.bf16.bf16 {%0,%1,%2,%3,%4,%5,%6,%7,%8,%9,%10,%11,%12,%13,%14,%15,%16,%17,%18,%19,%20,%21,%22,%23,%24,%25,%26,%27,%28,%29,%30,%31,%32,%33,%34,%35,%36,%37,%38,%39,%40,%41,%42,%43}, {%44,%45,%46,%47}, %48, p, 1, 1, 1;\n}\n" : "+f"(d[0]),"+f"(d[1]),"+f"(d[2]),"+f"(d[3]),"+f"(d[4]),"+f"(d[5]),"+f"(d[6]),"+f"(d[7]),"+f"(d[8]),"+f"(d[9]),"+f"(d[10]),"+f"(d[11]),"+f"(d[12]),"+f"(d[13]),"+f"(d[14]),"+f"(d[15]),"+f"(d[16]),"+f"(d[17]),"+f"(d[18]),"+f"(d[19]),"+f"(d[20]),"+f"(d[21]),"+f"(d[22]),"+f"(d[23]),"+f"(d[24]),"+f"(d[25]),"+f"(d[26]),"+f"(d[27]),"+f"(d[28]),"+f"(d[29]),"+f"(d[30]),"+f"(d[31]),"+f"(d[32]),"+f"(d[33]),"+f"(d[34]),"+f"(d[35]),"+f"(d[36]),"+f"(d[37]),"+f"(d[38]),"+f"(d[39]),"+f"(d[40]),"+f"(d[41]),"+f"(d[42]),"+f"(d[43]) : "r"(a0), "r"(a1), "r"(a2), "r"(a3), "l"(db), "r"(sc));
}
__device__ __forceinline__ void wgmma_rs_n80t(float (&d)[40], uint32_t a0, uint32_t a1, uint32_t a2, uint32_t a3, uint64_t db, int sc){
  asm volatile("{\n.reg .pred p;\nsetp.ne.b32 p, %45, 0;\nwgmma.mma_async.sync.aligned.m64n80k16.f32.bf16.bf16 {%0,%1,%2,%3,%4,%5,%6,%7,%8,%9,%10,%11,%12,%13,%14,%15,%16,%17,%18,%19,%20,%21,%22,%23,%24,%25,%26,%27,%28,%29,%30,%31,%32,%33,%34,%35,%36,%37,%38,%39}, {%40,%41,%42,%43}, %44, p, 1, 1, 1;\n}\n" : "+f"(d[0]),"+f"(d[1]),"+f"(d[2]),"+f"(d[3]),"+f"(d[4]),"+f"(d[5]),"+f"(d[6]),"+f"(d[7]),"+f"(d[8]),"+f"(d[9]),"+f"(d[10]),"+f"(d[11]),"+f"(d[12]),"+f"(d[13]),"+f"(d[14]),"+f"(d[15]),"+f"(d[16]),"+f"(d[17]),"+f"(d[18]),"+f"(d[19]),"+f"(d[20]),"+f"(d[21]),"+f"(d[22]),"+f"(d[23]),"+f"(d[24]),"+f"(d[25]),"+f"(d[26]),"+f"(d[27]),"+f"(d[28]),"+f"(d[29]),"+f"(d[30]),"+f"(d[31]),"+f"(d[32]),"+f"(d[33]),"+f"(d[34]),"+f"(d[35]),"+f"(d[36]),"+f"(d[37]),"+f"(d[38]),"+f"(d[39]) : "r"(a0), "r"(a1), "r"(a2), "r"(a3), "l"(db), "r"(sc));
}
__device__ __forceinline__ void wgmma_rs_n48(float (&d)[24], uint32_t a0, uint32_t a1, uint32_t a2, uint32_t a3, uint64_t db, int sc){
  asm volatile("{\n.reg .pred p;\nsetp.ne.b32 p, %29, 0;\nwgmma.mma_async.sync.aligned.m64n48k16.f32.bf16.bf16 {%0,%1,%2,%3,%4,%5,%6,%7,%8,%9,%10,%11,%12,%13,%14,%15,%16,%17,%18,%19,%20,%21,%22,%23}, {%24,%25,%26,%27}, %28, p, 1, 1, 0;\n}\n" : "+f"(d[0]),"+f"(d[1]),"+f"(d[2]),"+f"(d[3]),"+f"(d[4]),"+f"(d[5]),"+f"(d[6]),"+f"(d[7]),"+f"(d[8]),"+f"(d[9]),"+f"(d[10]),"+f"(d[11]),"+f"(d[12]),"+f"(d[13]),"+f"(d[14]),"+f"(d[15]),"+f"(d[16]),"+f"(d[17]),"+f"(d[18]),"+f"(d[19]),"+f"(d[20]),"+f"(d[21]),"+f"(d[22]),"+f"(d[23]) : "r"(a0), "r"(a1), "r"(a2), "r"(a3), "l"(db), "r"(sc));
}
__device__ __forceinline__ void wgmma_rs_n80(float (&d)[40], uint32_t a0, uint32_t a1, uint32_t a2, uint32_t a3, uint64_t db, int sc){
  asm volatile("{\n.reg .pred p;\nsetp.ne.b32 p, %45, 0;\nwgmma.mma_async.sync.aligned.m64n80k16.f32.bf16.bf16 {%0,%1,%2,%3,%4,%5,%6,%7,%8,%9,%10,%11,%12,%13,%14,%15,%16,%17,%18,%19,%20,%21,%22,%23,%24,%25,%26,%27,%28,%29,%30,%31,%32,%33,%34,%35,%36,%37,%38,%39}, {%40,%41,%42,%43}, %44, p, 1, 1, 0;\n}\n" : "+f"(d[0]),"+f"(d[1]),"+f"(d[2]),"+f"(d[3]),"+f"(d[4]),"+f"(d[5]),"+f"(d[6]),"+f"(d[7]),"+f"(d[8]),"+f"(d[9]),"+f"(d[10]),"+f"(d[11]),"+f"(d[12]),"+f"(d[13]),"+f"(d[14]),"+f"(d[15]),"+f"(d[16]),"+f"(d[17]),"+f"(d[18]),"+f"(d[19]),"+f"(d[20]),"+f"(d[21]),"+f"(d[22]),"+f"(d[23]),"+f"(d[24]),"+f"(d[25]),"+f"(d[26]),"+f"(d[27]),"+f"(d[28]),"+f"(d[29]),"+f"(d[30]),"+f"(d[31]),"+f"(d[32]),"+f"(d[33]),"+f"(d[34]),"+f"(d[35]),"+f"(d[36]),"+f"(d[37]),"+f"(d[38]),"+f"(d[39]) : "r"(a0), "r"(a1), "r"(a2), "r"(a3), "l"(db), "r"(sc));
}
template <int K> __device__ __forceinline__ void sched_fence(uint32_t a, uint32_t (&a0)[13][4]) {
  asm volatile("{\n.reg .pred p;\n.reg .b32 v;\nsetp.ne.u32 p, %52, %53;\n@p bra.uni SK%=;\nLP%=:\nld.volatile.shared.b32 v, [%52];\nsetp.eq.u32 p, v, 77;\n@p bra.uni LP%=;\nmov.b32 %0, v;\nmov.b32 %1, v;\nmov.b32 %2, v;\nmov.b32 %3, v;\nmov.b32 %4, v;\nmov.b32 %5, v;\nmov.b32 %6, v;\nmov.b32 %7, v;\nmov.b32 %8, v;\nmov.b32 %9, v;\nmov.b32 %10, v;\nmov.b32 %11, v;\nmov.b32 %12, v;\nmov.b32 %13, v;\nmov.b32 %14, v;\nmov.b32 %15, v;\nmov.b32 %16, v;\nmov.b32 %17, v;\nmov.b32 %18, v;\nmov.b32 %19, v;\nmov.b32 %20, v;\nmov.b32 %21, v;\nmov.b32 %22, v;\nmov.b32 %23, v;\nmov.b32 %24, v;\nmov.b32 %25, v;\nmov.b32 %26, v;\nmov.b32 %27, v;\nmov.b32 %28, v;\nmov.b32 %29, v;\nmov.b32 %30, v;\nmov.b32 %31, v;\nmov.b32 %32, v;\nmov.b32 %33, v;\nmov.b32 %34, v;\nmov.b32 %35, v;\nmov.b32 %36, v;\nmov.b32 %37, v;\nmov.b32 %38, v;\nmov.b32 %39, v;\nmov.b32 %40, v;\nmov.b32 %41, v;\nmov.b32 %42, v;\nmov.b32 %43, v;\nmov.b32 %44, v;\nmov.b32 %45, v;\nmov.b32 %46, v;\nmov.b32 %47, v;\nmov.b32 %48, v;\nmov.b32 %49, v;\nmov.b32 %50, v;\nmov.b32 %51, v;\nSK%=:\n}"
    : "+r"(a0[0][0]), "+r"(a0[0][1]), "+r"(a0[0][2]), "+r"(a0[0][3]), "+r"(a0[1][0]), "+r"(a0[1][1]), "+r"(a0[1][2]), "+r"(a0[1][3]), "+r"(a0[2][0]), "+r"(a0[2][1]), "+r"(a0[2][2]), "+r"(a0[2][3]), "+r"(a0[3][0]), "+r"(a0[3][1]), "+r"(a0[3][2]), "+r"(a0[3][3]), "+r"(a0[4][0]), "+r"(a0[4][1]), "+r"(a0[4][2]), "+r"(a0[4][3]), "+r"(a0[5][0]), "+r"(a0[5][1]), "+r"(a0[5][2]), "+r"(a0[5][3]), "+r"(a0[6][0]), "+r"(a0[6][1]), "+r"(a0[6][2]), "+r"(a0[6][3]), "+r"(a0[7][0]), "+r"(a0[7][1]), "+r"(a0[7][2]), "+r"(a0[7][3]), "+r"(a0[8][0]), "+r"(a0[8][1]), "+r"(a0[8][2]), "+r"(a0[8][3]), "+r"(a0[9][0]), "+r"(a0[9][1]), "+r"(a0[9][2]), "+r"(a0[9][3]), "+r"(a0[10][0]), "+r"(a0[10][1]), "+r"(a0[10][2]), "+r"(a0[10][3]), "+r"(a0[11][0]), "+r"(a0[11][1]), "+r"(a0[11][2]), "+r"(a0[11][3]), "+r"(a0[12][0]), "+r"(a0[12][1]), "+r"(a0[12][2]), "+r"(a0[12][3]) : "r"(a), "n"(4 * K) : "memory");
}
constexpr int CONV_SLOTS = 10;

struct cf { float x, y; };
__device__ __forceinline__ cf cmul(cf a, cf b) { cf r; r.x = fmaf(a.x, b.x, -(a.y * b.y)); r.y = fmaf(a.x, b.y, a.y * b.x); return r; }
__device__ __forceinline__ cf anchor(float e2, float ang) {
  const float mag = ex2f(e2);
  cf z; z.x = mag * __cosf(ang); z.y = mag * __sinf(ang); return z;
}
__device__ __forceinline__ void st_chunk(uint32_t are, const cf (&v)[8]) {
  sts128(are, pack2(v[0].x, v[1].x), pack2(v[2].x, v[3].x), pack2(v[4].x, v[5].x), pack2(v[6].x, v[7].x));
  sts128(are + 3584, pack2(v[0].y, v[1].y), pack2(v[2].y, v[3].y), pack2(v[4].y, v[5].y), pack2(v[6].y, v[7].y));
}
__device__ __forceinline__ void tables(const uint32_t tab, const int lane, const uint32_t (&pe)[4], const uint32_t (&po)[2], const uint32_t (&px)[4], const uint32_t k0) {
  const int g = lane >> 2, t = lane & 3;
#pragma unroll
  for (int i = 0; i < 3; i++) sts128(tab + (i == 2 && lane >= 24 ? (lane & 3) * 16 : 4160 + i * 512 + lane * 16), 0, 0, 0, 0);
  __syncwarp();
  const uint32_t sel = lane ? 0x3210 : 0x1076;
  uint32_t last = k0;
  if (!lane) sts32(tab + 60, k0 >> 16);
#pragma unroll
  for (int j = 0; j < 4; j++) {
    const uint32_t sh = __shfl_sync(0xffffffffu, pe[j], lane - 1), pv = __byte_perm(sh, last, sel), md = j < 2 ? po[j & 1] : ((lane & 1) ? pe[j] : pv);
    last = sh;
    sts64(tab + 64 + 512 * j + 8 * lane, __byte_perm(md, pv, 0x5410), __byte_perm(pe[j], md, 0x5410));
    sts64(tab + 320 + 512 * j + 8 * lane, __byte_perm(md, pv, 0x7632), __byte_perm(pe[j], md, 0x7632));
  }
  const uint32_t d3 = tab + 2112 + 16 * t + 32 * g, d4 = tab + 4416 + 288 * (g & 1) + 2 * (8 + 32 * t + (g >> 1));
#pragma unroll
  for (int j = 0; j < 4; j++) {
    const uint32_t sh = __shfl_sync(0xffffffffu, px[j], lane - (t ? 1 : 3)), pv = __byte_perm(sh, last, sel), c = px[j], m = t ? c : pv;
    last = sh;
    if (t < 2) {
      sts128(d3 + 512 * j, __byte_perm(pv, 0, 0x1010), __byte_perm(m, pv, 0x5410), __byte_perm(c, m, 0x5410), __byte_perm(c, 0, 0x1010));
      sts128(d3 + 512 * j + 256, __byte_perm(pv, 0, 0x3232), __byte_perm(m, pv, 0x7632), __byte_perm(c, m, 0x7632), __byte_perm(c, 0, 0x3232));
    } else {
      sts16(d4 + 16 * j, c); sts16(d4 + 16 * j + 584, c);
      sts16(d4 + 16 * j + 8, c >> 16); sts16(d4 + 16 * j + 592, c >> 16);
    }
  }
  if (lane == 29) {
    const uint32_t c = __byte_perm(px[3], 0, 0x3232);
    sts128(tab + 4160, c, c, c, c);
    sts32(tab + 4176, c << 16);
  }
  fence_async_s();
  __syncwarp();
  if (elect()) mbar_arrive(B_TB);
}
__device__ __forceinline__ void lda4(uint32_t (&a)[4], uint32_t p) { a[0] = lds32(p); a[1] = lds32(p + 32); a[2] = lds32(p - 32); a[3] = lds32(p); }

__global__ void __launch_bounds__(512, 1) fused_kernel(const __grid_constant__ Params p) {
  extern __shared__ __align__(1024) uint8_t smraw[];
  const int tid = threadIdx.x, lane = tid & 31;
  const int warp = __shfl_sync(0xffffffffu, tid >> 5, 0);
  const int b = blockIdx.x, hg = b & 7, rb = b >> 3;
  const int g = lane >> 2, t = lane & 3;
  auto tile = [&](const uint32_t s, const int kk, const uint32_t extra) {
    const uint32_t st = SB + s * STG, fb = B_FULL + 8 * s;
    mbar_expect(fb, STG + extra);
    tma2(st, &p.mx, fb, kk * 64, rb * 128);
    tma3(st + 16384, &p.mw64, fb, hg * 80, kk * 64, 0);
    tma3(st + 40960, &p.mw16, fb, hg * 80 + 64, kk * 64, 0);
  };
  auto slice = [&](int i) { return i ? i - (i <= hg) : hg; };
  float acc[5][4], k0 = 0.f;
  if (warp == 12) {
    if (elect()) {
      TS(120);
#pragma unroll
      for (int i = 0; i < 16; i++) mbar_init(A_BAR + 8 * i + (i == 15 ? 16 : 0), i < 7 ? (i == 5 ? 2 : 8) : (i < 10 ? 4 + (i == 7) : 1));
      mbar_init(B_FULL + 16, 1);
      mbar_init(B_G, 8);
      mbar_init(B_C1, 8);
      fence_async_s();
      TS(113);
      tile(0, 0, 1280);
      bulk_g2s(A_GW, p.gatew, 1280, B_FULL);
      tile(1, 1, 0);
      TS(116);
    }
    __syncwarp();
    uint32_t e;
    asm volatile("ld.relaxed.gpu.global.u32 %0, [%1];" : "=r"(e) : "l"(g_s.cnt) : "memory");
    e = (e >> 9) & 1;
#pragma unroll
    for (int i = 0; i < 5; i++) sts128(A_EM + i * 512 + lane * 16, e, e, e, e);
    fence_async_s();
    bar_sync(9, 512);
    if (elect()) {
      TS(114);
      asm volatile("cp.async.bulk.prefetch.tensor.2d.L2.global [%0, {%1,%2}];" ::"l"(&p.mx), "r"(hg * 64 + 128), "r"(rb * 128) : "memory");
      asm volatile("cp.async.bulk.prefetch.tensor.3d.L2.global [%0, {%1,%2,%3}];" ::"l"(&p.mw64 + (rb >> 3)), "r"(hg * 80 + (rb >> 3) * 64), "r"((rb & 7) * 64 + 128), "r"(0) : "memory");
      bulk_s2g(g_s.kv + b * 3840, A_EM, 2560);
      bulk_s2g(g_s.kv + b * 3840 + 2560, A_EM, 1280);
#pragma unroll 1
      for (int i = 0; i < 20480; i += 2560) {
        bulk_s2g(g_s.o + b * 20480 + i, A_EM, 2560);
        bulk_s2g(g_s.aT + b * 20480 + i, A_EM, 2560);
      }
      bulk_commit();
      TS(112);
      asm volatile("cp.async.bulk.wait_group 0;" ::: "memory");
      TS(17);
    }
    __syncwarp();
    bar_sync(0, 512);
  } else {
    const int ch = warp < 12 ? warp & 3 : 4, base = 64 * (warp < 12 ? warp >> 2 : warp - 13), gi = warp - 4 - (warp > 12);
    const uint32_t gch = 5 * b + ch, i0 = gch * 192 + base + 2 * lane;
    uint32_t cur[8];
    cur[0] = ldg32(p.Are + i0); cur[1] = ldg32(p.Aim + i0); cur[2] = ldg32(p.Bre + i0);
    cur[3] = ldg32(p.Bim + i0); cur[4] = ldg32(p.Cre + i0); cur[5] = ldg32(p.Cim + i0);
    cur[6] = ldg16(p.logdt + gch);
    if (warp < 7) asm volatile("prefetch.tensormap [%0];" ::"l"(&p.mx + warp) : "memory");
    const uint32_t buf = warp < 4 ? A_TAB + (warp == 2 ? 29952 : (warp == 3 ? 14336 : 7168 * warp)) : (gi < 10 ? SB + 2 * STG + 7168 * gi : A_TAB + 37120);
    const uint32_t ar = buf + lane * 112, adA = buf + (((lane >> 4) << 3) + (lane & 7)) * 112 + ((lane >> 3) & 1) * 16;
    const float dt = bflo(pack2(expf(bflo(cur[6])), 0.f));
#pragma unroll
    for (int c = 0; c < 5; c++) acc[c][0] = acc[c][1] = acc[c][2] = acc[c][3] = 0.f;
    if (tid == 0) TS(16);
#pragma unroll 1
    for (int it = 0; it < 2; it++) {
      const float a2 = dt * bflo(cur[0]) * 1.4426950408889634f, bb = dt * bflo(cur[1]);
      const cf CB = cmul({bflo(cur[4]), bflo(cur[5])}, {dt * bflo(cur[2]), dt * bflo(cur[3])});
      if (!it && __float_as_uint(a2 * CB.x) != 0x7fc12345u) bar_arrive(9, 512);
#pragma unroll
      for (int i = 0; i < 6; i++) cur[i] >>= 16;
      const cf z1 = anchor(a2, bb), z64 = anchor(a2 * 64.f, bb * 64.f), z64c = {z64.x, -z64.y};
      const cf w = cmul(z64, z64), w2 = cmul(w, w), w4 = cmul(w2, w2);
      k0 += CB.x;
      cf v[8], e[8];
      v[0] = cmul(z1, z1); v[2] = cmul(v[0], v[0]); v[6] = cmul(v[2], v[2]);
      const cf z8c = {v[6].x, -v[6].y};
      e[0] = z1; e[2] = cmul(v[0], z1); e[4] = cmul(v[2], z1); e[6] = cmul(v[2], e[2]);
      v[4] = cmul(e[2], e[2]); v[1] = cmul(v[2], w4); v[3] = cmul(v[6], w4); v[5] = cmul(v[3], w4); v[7] = cmul(v[5], w4);
#pragma unroll
      for (int i = 0; i < 8; i += 2) e[i + 1] = cmul(e[i], w);
      st_chunk(ar + 96, e);
      e[0].x = CB.x; e[0].y = -CB.y;
      st_chunk(ar + 32, v);
#pragma unroll
      for (int i = 1; i < 8; i++) e[i] = cmul(e[i - 1], z8c);
#pragma unroll
      for (int i = 0; i < 8; i++) v[i] = cmul(v[i], w);
      st_chunk(ar + 48, v);
#pragma unroll
      for (int i = 0; i < 8; i++) v[i] = cmul(v[i], w);
      st_chunk(ar + 64, v);
      st_chunk(ar, e);
#pragma unroll
      for (int i = 0; i < 8; i++) v[i] = cmul(v[i], w);
      st_chunk(ar + 80, v);
#pragma unroll
      for (int i = 0; i < 8; i++) e[i] = cmul(e[i], z64c);
      st_chunk(ar + 16, e);
      __syncwarp();
      uint32_t FA[2][2][4], FB[2][5][4];
#pragma unroll
      for (int j = 0; j < 2; j++) {
        ldsm4t(FA[j][0], adA + j * 3584);
        ldsm4t(FA[j][1], adA + j * 3584 + 1792);
#pragma unroll
        for (int c = 0; c < 5; c++) ldsm4t(FB[j][c], ar + 32 + j * 3584 + 16 * c);
      }
      __syncwarp();
#pragma unroll
      for (int j = 0; j < 2; j++)
#pragma unroll
        for (int h = 0; h < 2; h++)
#pragma unroll
          for (int c = 0; c < 5; c++) mma(acc[c], FA[j][h], FB[j][c][2 * h], FB[j][c][2 * h + 1]);
      if (tid == 32) TS(80 + it);
    }
#pragma unroll
    for (int i = 1; i < 32; i *= 2) k0 += __shfl_xor_sync(0xffffffffu, k0, i);
    if (warp >> 2 != 2) {
      const uint32_t pa = (warp < 4 ? buf + (warp == 3 ? 2368 : 0) : (warp < 8 ? A_P4 - 4 * 2560 : A_PH - 13 * 2560) + warp * 2560) + lane * 16;
#pragma unroll
      for (int c = 0; c < 5; c++) sts128f(pa + c * 512, acc[c]);
      if (lane == 0) sts32(A_DUM + 4 * warp, __float_as_uint(k0));
    }
    if (lane == 0) TS(88 + (warp & 3) + (warp >> 3) * 4);
    bar_sync(0, 512);
    if (tid == 0) TS(15);
  }

  if (warp >= 12) {
    asm volatile("setmaxnreg.dec.sync.aligned.u32 40;");
    if (warp == 12) {
      if (elect()) {
        uint32_t s = 0, ph = 0;
        fence_async_s();
        tile(2, 2, 0);
        mbar_expect(B_XS, 20480);
        tma2(A_U, &p.mxs, B_XS, hg * 80, rb * 128);
        TS(30);
#pragma unroll 1
        for (int kt = 3; kt < 10; kt++) {
          mbar_wait(B_EMPTY + 8 * s, ph);
          tile(s, kt, 0);
          if (++s == 3) { s = 0; ph ^= 1; }
        }
        uint32_t bar = B_WO - 8;
#pragma unroll 1
        for (int i = 0; i < 8; i++) {
          if (!(i & 3)) {
            bar += 8;
            mbar_wait(i ? (C1P < 2 ? B_C1 : B_C2) : B_W1D, 0);
            mbar_expect(bar, 4 * WOP);
          }
          if (i > 4) __nanosleep(WSL);
          tma3(A_WO + i * WOP, &p.mwo, bar, 0, 80 * slice(i), 5 * hg);
        }
        TS(24);
      }
    } else {
      if (warp == 13) {
        const float dsk = bflo(ldg16(p.dskip + 5 * b + 4));
        uint32_t pe[4], po[2], px[4];
#pragma unroll
        for (int j = 0; j < 5; j++) {
          float s[4], u[4];
          lds128f(s, A_PH + j * 512 + lane * 16);
#pragma unroll
          for (int w = 1; w < 3; w++) { lds128f(u, A_PH + w * 2560 + j * 512 + lane * 16); s[0] += u[0]; s[1] += u[1]; s[2] += u[2]; s[3] += u[3]; }
          if (j < 4) { pe[j & 3] = pack2(s[0], s[2]); px[j & 3] = pack2(s[1], s[3]); }
          else { po[0] = pack2(s[0], s[2]); po[1] = pack2(s[1], s[3]); }
        }
        float kp[4];
        lds128f(kp, A_DUM + 48);
        __syncwarp();
        tables(A_TAB + 4 * TABP, lane, pe, po, px, pack2(0.f, kp[1] + (kp[2] + kp[3]) + dsk));
        if (lane == 0) TS(18);
      } else {
        const uint32_t a = A_U + ((lane & 4) * 4 + 2 * (lane >> 3) + (lane & 1)) * 160 + (lane & 2) * 40;
        const uint32_t d = A_XT + ((t & 1) * 40 + g) * 256 + (((t >> 1) ^ (2 * (g & 3)) ^ (warp & 1)) << 4) + (warp & 1) * 128;
        mbar_wait(B_XS, 0);
        if (tid == 448) TS(110);
#pragma unroll 1
        for (int r = 0; r < 4; r++) {
          uint32_t X[5][4];
#pragma unroll
          for (int i = 0; i < 5; i++) ldsm4t(X[i], a + r * 5120 + (warp & 1) * 1280 + i * 16);
          if (!r) mbar_wait(B_TB, 0);
#pragma unroll
          for (int i = 0; i < 5; i++) sts128((d ^ (r * 32)) + i * 2048, X[i][0], X[i][1], X[i][2], X[i][3]);
        }
        fence_async_s();
        __syncwarp();
        if (lane == 0) TS(104 + warp);
        if (elect()) mbar_arrive(B_UT);
      }
      if (warp == 15) {
        if ((uint32_t)__cvta_generic_to_shared(smraw) != SB) __trap();
        const bool me = elect();
        uint32_t tg = 0;
        if (me) {
          mbar_wait_b(B_UT, 0, 1000000);
          TS(20);
#pragma unroll 1
          for (int i = 0; i < 80; i += UBX) {
            if (i) __nanosleep(USL);
            asm volatile("cp.async.bulk.tensor.3d.global.shared::cta.bulk_group [%0, {%2,%3,%4}], [%1];" ::"l"(&p.mut), "r"(A_XT + i * 256), "r"(384 + rb * 64), "r"(0), "r"(hg * 80 + i) : "memory");
          }
          bulk_commit();
          asm volatile("cp.async.bulk.wait_group 0;" ::: "memory");
          TS(19);
          asm volatile("atom.relaxed.gpu.global.add.u32 %0, [%1], 4;" : "=r"(tg) : "l"(g_s.cnt) : "memory");
          sts32(A_TAG, (tg >> 9) & 1);
          TS(28);
        }
        __syncwarp();
        if (me) {
          flag_wait((tg | 511) + 1);
          fence_async_g();
          TS(25);
          mbar_expect(B_U, 5 * UP);
          bulk_g2s(A_U, g_s.uT + b * (5 * UP), 5 * UP, B_U);
          mbar_wait_b(B_DONE, 0, 1000000);
        }
      } else {
        const int rho = tid - 416, hf = rho & 1;
        char* og = g_s.aT + b * 20480 + rho * 16;
        mbar_wait(B_U, 0);
        sts128(A_PART + (lane >> 3) * 4096 + (lane & 4) * 528 + (lane & 3) * 16, 0, 0, 0, 0);
#pragma unroll 1
        for (int c = 0; c < 5; c++) {
          bar_arrive(6, 192);
          bar_sync(5, 192);
          const uint32_t old = lds32(A_TAG);
          uint32_t rd = A_PART + hf * 2048 + (((rho >> 1) ^ (4 * hf)) << 4);
#pragma unroll 1
          for (int r = 0; r < 4; r++, rd += 512, og += 1024) {
            const uint4 x0 = lds128(rd), x1 = lds128(rd + 4096), x2 = lds128(rd + 8192), x3 = lds128(rd + 12288);
            st_unit(og, tagged(hadd2(hadd2(x0.x, x1.x), hadd2(x2.x, x3.x)), old), hadd2(hadd2(x0.y, x1.y), hadd2(x2.y, x3.y)),
                    hadd2(hadd2(x0.z, x1.z), hadd2(x2.z, x3.z)), hadd2(hadd2(x0.w, x1.w), hadd2(x2.w, x3.w)));
          }
        }
        bar_arrive(3, 192);
        if (tid == 416) TS(29);
      }
    }
  } else if (warp < 8) {
    asm volatile("setmaxnreg.inc.sync.aligned.u32 168;");
    const int wg = warp >> 2;
    const uint32_t l8 = (lane & 7) * 16, lb = (lane >> 3) & 1, lh = lane >> 4;
    uint32_t gg0, gg1;
    float d[124];
    {
      uint32_t s = 0, ph = 0, F[2][2][4];
      const uint32_t xa = SB + (warp * 16 + (lane & 15)) * 128, xs = (lh ^ (lane & 7)) << 4;
      uint32_t gd = dlo(A_GW, 16);
      auto group = [&](const int h, const uint32_t so, const int first) {
        wg_fence();
#pragma unroll
        for (int k = 0; k < 2; k++) {
          const int ks = 2 * h + k;
          wgmma_rs_n192(d, F[h][k][0], F[h][k][1], F[h][k][2], F[h][k][3], desc(dlo(SB + 16384 + ks * 2048, 8192) + so, dhi(1024, 1)), ks | first);
          wgmma_rs_n48t(d, F[h][k][0], F[h][k][1], F[h][k][2], F[h][k][3], desc(dlo(SB + 40960 + ks * 512, 2048) + so, dhi(256, 3)), ks | first);
          wgmma_rs_n8(d, F[h][k][0], F[h][k][1], F[h][k][2], F[h][k][3], desc(gd + 2 * ks, dhi(128, 0)), ks | first);
        }
        wg_commit();
      };
      mbar_wait(B_FULL, 0);
      if (tid == 0) TS(60);
      ldsm4(F[0][0], xa + xs); ldsm4(F[0][1], xa + (xs ^ 32));
#pragma unroll 1
      for (int kt = 0; kt < 10; kt++) {
        const uint32_t so = s * (STG >> 4), sp = s ? s - 1 : 2;
        group(0, so, kt);
        wg_wait<1>();
        if (elect() && kt) mbar_arrive(B_EMPTY + 8 * sp);
        ldsm4(F[1][0], xa + s * STG + (xs ^ 64)); ldsm4(F[1][1], xa + s * STG + (xs ^ 96));
        group(1, so, 1);
        if (++s == 3) { s = 0; ph ^= 1; }
        gd += 8;
        wg_wait<1>();
        if (tid == 0) TS(70 + kt);
        if (kt == 9) break;
        mbar_wait(B_FULL + 8 * s, ph);
        if (tid == 0) TS(61 + kt);
        ldsm4(F[0][0], xa + s * STG + xs); ldsm4(F[0][1], xa + s * STG + (xs ^ 32));
      }
      wg_wait<0>();
    }
    pin(d);
    if (elect()) mbar_arrive(B_W1D);
    if (tid == 0) TS(2);
    if (tid == 128) TS(31);
    uint32_t P[5][4], Q[5][4];
#pragma unroll
    for (int ks = 0; ks < 5; ks++)
#pragma unroll
      for (int i = 0; i < 4; i++) {
        const int jq = (ks < 4 ? 8 * ks : 96) + 2 * i, jk = (ks < 4 ? 32 + 8 * ks : 104) + 2 * i;
        Q[ks][i] = pack2(d[jq], d[jq + 1]);
        P[ks][i] = pack2(d[jk], d[jk + 1]);
      }
    mbar_wait(B_EMPTY + 16, 0);
    {
#pragma unroll
      for (int i = 0; i < 4; i++)
        if (i < 3 || tid < 112) sts128(A_B88 + i * 4096 + tid * 16, 0, 0, 0, 0);
      const uint32_t stv = A_V + warp * 3072 + lb * 1536 + lh * 128 + l8;
#pragma unroll
      for (int ks = 0; ks < 5; ks++) {
        const int j = ks < 4 ? 64 + 8 * ks : 112;
        stsm4(stv + ks * 256 + (ks == 2 ? lh * 128 : (ks > 2 ? 128 : 0)), pack2(d[j], d[j + 1]), pack2(d[j + 2], d[j + 3]), pack2(d[j + 4], d[j + 5]), pack2(d[j + 6], d[j + 7]));
      }
      sts128(stv + 640 + lh * 640, 0x3F803F80u, 0x3F803F80u, 0x3F803F80u, 0x3F803F80u);
      const uint32_t gp = __shfl_sync(0xffffffffu, pack2(rcpf(1.f + ex2f(-1.4426950408889634f * d[120])), rcpf(1.f + ex2f(-1.4426950408889634f * d[122]))), lane & ~3);
      gg0 = __byte_perm(gp, 0, 0x1010);
      gg1 = __byte_perm(gp, 0, 0x3232);
    }
    const int w4 = warp & 3;
    const int u = min(tid, 239), blk = (u * 205) >> 14, r = u - 80 * blk, w2 = r >= 40, hd = r - 40 * w2 >= 20;
    const char* kq = g_s.kv + hg * 3840 + u * 16;
    uint32_t X[16][4], old;
    {
#pragma unroll
      for (int ks = 0; ks < 5; ks++)
#pragma unroll
        for (int i = 0; i < 4; i++) P[ks][i] = phi2(P[ks][i], 0);
      const uint32_t sta = A_K + warp * 2560 + (lb * 10 + lh) * 128 + l8;
#pragma unroll
      for (int ks = 0; ks < 5; ks++) stsm4(sta + ks * 256, P[ks][0], P[ks][1], P[ks][2], P[ks][3]);
      fence_async_s();
      bar_sync(1, 256);
      if (tid == 0) TS(3);
      float kv[24];
      wg_fence();
#pragma unroll
      for (int ks = 0; ks < 8; ks++)
        wgmma_ss_n48(kv, desc(dlo(A_K + ks * 2560, 1280) + wg * 40, dhi(128, 0)), desc(dlo(A_V + ks * 3072, 1536) + wg * 48, dhi(128, 0)), ks);
      wg_commit();
      mbar_wait(B_U, 0);
      old = lds32(A_TAG);
      wg_wait<0>();
      pin(kv);
      if (C1P == 0 && elect()) mbar_arrive(B_C1);
      uint32_t zero;
      {
        uint32_t m[6];
#pragma unroll
        for (int h = 0; h < 2; h++) {
          const bool hd = 16 * w4 + g + 8 * h >= 20, zt = (t >= 2) != hd;
          m[3 * h] = pack2(hd ? kv[12 + 2 * h] : kv[2 * h], hd ? kv[13 + 2 * h] : kv[1 + 2 * h]);
          m[3 * h + 1] = pack2(hd ? kv[16 + 2 * h] : kv[4 + 2 * h], hd ? kv[17 + 2 * h] : kv[5 + 2 * h]);
          m[3 * h + 2] = pack2(zt ? kv[20 + 2 * h] : kv[8 + 2 * h], kv[9 + 2 * h]);
        }
        const uint32_t sc = A_B88 + 14336 + warp * 768 + lane * 16;
        stsm4(sc, m[0], m[1], m[2], m[3]);
        stsm2(sc + 512, m[4], m[5]);
        __syncwarp();
        const uint4 u0 = lds128(sc), u1 = lds128(sc + 512);
        char* kp = g_s.kv + b * 3840 + (40 * wg + 16 * w4 + (lane & 7)) * 16;
        if (2 * w4 + (lane >= 24) < 5) st_unit(kp + (lane < 24 ? (lane >> 3) * 1280 : 128), tagged(u0.x, old), u0.y, u0.z, u0.w);
        if (lane < 16 && w4 < 2) st_unit(kp + (lane >> 3) * 1280 + 1408, tagged(u1.x, old), u1.y, u1.z, u1.w);
        zero = __byte_perm(u0.x, 0, gridDim.x * 0x88 + 0x44);
      }
      const char* kpp = g_s.kv + hg * 3840 + (((lane & 15) == rb ? rb ^ 1 : lane & 15)) * 30720 + warp * 512 + 112;
      uint32_t pv;
      asm volatile("ld.relaxed.gpu.global.b32 %0, [%1];" : "=r"(pv) : "l"(kpp) : "memory");
      if (tid == 0) TS(4);
#pragma unroll
      for (int ks = 0; ks < KSP; ks++)
#pragma unroll
        for (int i = 0; i < 4; i++) { P[ks][i] = phi2(Q[ks][i], zero); asm volatile("" : "+r"(P[ks][i])); }
      const bool early = __all_sync(0xffffffffu, (pv ^ old) & 1);
      if (early) {
#pragma unroll
        for (int s = 0; s < 16; s++) ld_unit(X[s], kq + s * 30720);
      }
#pragma unroll
      for (int ks = KSP; ks < 5; ks++)
#pragma unroll
        for (int i = 0; i < 4; i++) { P[ks][i] = phi2(Q[ks][i], zero); asm volatile("" : "+r"(P[ks][i])); }
      if (tid == 0) TS(26);
      {
        const int q = tid & 63, h = (tid >> 6) & 1;
        const uint32_t ub = A_U + (PG + wg) * UP + 768 - 16 + q * 16;
        pool(ub + (h ? 0 : UP / 2 - 16), ub + h * (UP / 2), A_PB + wg * 4096 + h * 1024 + (8 * (q & 7) + (((q >> 3) + q) & 7)) * 16);
        bar_arrive(7, 384);
      }
      if (tid == 0) TS(56);
      if (!early) {
        poll_tag(kpp, old);
#pragma unroll
        for (int s = 0; s < 16; s++) ld_unit(X[s], kq + s * 30720);
      }
      if (tid == 0) TS(54);
    }
    {
      float v[8];
      int spin = 0; (void)spin;
#pragma unroll 1
      for (;;) {
        uint32_t ok = 1;
#pragma unroll
        for (int s = 0; s < 16; s++) ok &= X[s][0] ^ old;
        if (ok) break;
        __nanosleep(KSLEEP);
#pragma unroll
        for (int s = 0; s < 16; s++) re_unit(X[s], kq + s * 30720, old);
        SPIN_GUARD(spin)
      }
      if (tid == 0) TS(5);
      if (C1P == 1 && elect()) mbar_arrive(B_C1);
#pragma unroll
      for (int i = 0; i < 4; i++) {
        v[2 * i] = bflo(X[0][i]); v[2 * i + 1] = bfhi(X[0][i]);
#pragma unroll
        for (int s = 1; s < 16; s++) { v[2 * i] += bflo(X[s][i]); v[2 * i + 1] += bfhi(X[s][i]); }
      }
      const uint32_t ra = A_B88 + (r >> 3) * 1408 + (r & 7) * 16;
      uint32_t q0 = pack2(v[0], v[1]), q1 = pack2(v[2], v[3]), q2 = pack2(v[4], v[5]), q3 = pack2(v[6], v[7]);
      if (blk == 2) {
        sts16(ra + 1280 + 4 * w2 + 2 * hd, hd ? q1 : q3);
        if (hd) q0 = q1 = 0; else q2 = q3 = 0;
      }
      sts128(ra + w2 * 640 + (blk == 2 ? 256 : blk * 128 + hd * 384), q0, q1, q2, q3);
    }
    fence_async_s();
    bar_sync(1, 256);
    if (tid == 0) TS(27);
    uint32_t A[4][5][4];
    {
      float o[44];
      wg_fence();
#pragma unroll
      for (int ks = 0; ks < 5; ks++)
        wgmma_rs_n88(o, P[ks][0], P[ks][1], P[ks][2], P[ks][3], desc(dlo(A_B88 + ks * 2816, 1408), dhi(128, 0)), ks);
      wg_commit();
      const float n0 = 1.f - bflo(gg0), n1 = 1.f - bflo(gg1);
      wg_wait<0>();
      pin(o);
      if (tid == 0) TS(39);
      if (elect()) mbar_arrive(B_C2);
      float rc[4], r0[4], r1[4];
#pragma unroll
      for (int i = 0; i < 4; i++) rc[i] = (i < 2 ? n0 : n1) * rcpf(o[40 + i] + 1e-6f);
#pragma unroll
      for (int h = 0; h < 4; h++) {
        r0[h] = __shfl_sync(0xffffffffu, rc[h & 1], (lane & ~3) | (h >> 1));
        r1[h] = __shfl_sync(0xffffffffu, rc[2 + (h & 1)], (lane & ~3) | (h >> 1));
      }
#pragma unroll
      for (int j = 0; j < 10; j++) {
        float m0, m1;
        if (j == 2) { m0 = t < 2 ? r0[0] : r0[1]; m1 = t < 2 ? r1[0] : r1[1]; }
        else if (j == 7) { m0 = t < 2 ? r0[2] : r0[3]; m1 = t < 2 ? r1[2] : r1[3]; }
        else { m0 = r0[(8 * j) / 20]; m1 = r1[(8 * j) / 20]; }
        A[0][j >> 1][(j & 1) * 2] = pack2(o[4 * j] * m0, o[4 * j + 1] * m0);
        A[0][j >> 1][(j & 1) * 2 + 1] = pack2(o[4 * j + 2] * m1, o[4 * j + 3] * m1);
      }
    }
    const char* ob = g_s.o + rb * 163840 + warp * 2560 + lane * 16;
#pragma unroll
    for (int ks = 0; ks < 5; ks++) {
      A[0][ks][0] = tagged(A[0][ks][0], old);
      st_unit((char*)ob + hg * 20480 + ks * 512, A[0][ks][0], A[0][ks][1], A[0][ks][2], A[0][ks][3]);
    }
    if (tid == 0) TS(6);
    poll_tag(ob + ((lane & 7) == hg ? hg ^ 1 : lane & 7) * 20480 + 2544 - lane * 16, old);
    if (tid == 0) TS(55);
    mbar_wait(B_TF, 0);
    uint32_t wo = warp * 2560 + lane * 16;
    asm volatile("" : "+r"(wo));
    auto fetch = [&](uint32_t (&X)[5][4], uint32_t k) {
      const char* s = g_s.o + (rb * 8 + slice(k)) * 20480;
#pragma unroll
      for (int ks = 0; ks < 5; ks++) ld_unit(X[ks], s + ks * 512 + wo);
    };
    if (tid == 0) TS(37);
    float y[40];
#pragma unroll 1
    for (int hf = 0; hf < 2; hf++) {
#pragma unroll
      for (int q = 0; q < 4; q++) {
        int spin = 0; (void)spin;
        const uint32_t k = 4 * hf + q;
        for (;;) {
          const uint32_t o2 = lds32(A_TAG);
          uint32_t ok = 1;
#pragma unroll
          for (int ks = 0; ks < 5; ks++) asm volatile("lop3.b32 %0, %0, %1, %2, 0x60;" : "+r"(ok) : "r"(A[q][ks][0]), "r"(o2));
          if (__all_sync(0xffffffffu, ok)) break;
          const char* sp = ob + slice(k) * 20480;
          poll_tag(sp + 2544 - lane * 16, old);
#pragma unroll
          for (int ks = 0; ks < 5; ks++) re_unit(A[q][ks], sp + ks * 512, old);
          SPIN_GUARD(spin)
        }
        if (tid == 0) TS((hf ? 105 : 121) + q);
        if (q == (GP & 3) && hf == (GP >> 2) && elect()) mbar_arrive(B_G);
        if (q == 0) mbar_wait(B_WO + 8 * hf, 0);
        const uint32_t bo = k * (WOP >> 4);
        wg_fence();
#pragma unroll
        for (int ks = 0; ks < 5; ks++)
          wgmma_rs_n80t(y, A[q][ks][0], A[q][ks][1], A[q][ks][2], A[q][ks][3], desc(dlo(A_WO + ks * 512, 2560) + bo, dhi(256, 3)), (q | ks) ? 1 : hf);
        wg_commit();
        if (q == 0 && !hf) { fetch(A[1], 1); fetch(A[2], 2); fetch(A[3], 3); }
        wg_wait<1>();
        if (q ? !hf : hf) fetch(A[(q + 3) & 3], k + 3);
      }
    }
    wg_wait<0>();
    pin(y);
    if (tid == 0) TS(10);
    mbar_wait(B_AT, 0);
    if (tid == 0) TS(11);
    {
      const uint32_t tb = A_Q + warp * 2560;
      const uint32_t aa = tb + lh * 256 + ((((lane & 7) * 2 + (lb ^ (g & 1))) ^ ((warp & 3) << 1)) << 4);
      uint32_t a[5][4];
#pragma unroll
      for (int jj = 0; jj < 5; jj++) ldsm4t(a[jj], aa + jj * 512);
      __syncwarp();
      const uint32_t sa = tb + (lane & 15) * 160 + lh * 16;
      auto mix = [](uint32_t gq, uint32_t av, uint32_t c) { uint32_t r; asm("fma.rn.bf16x2 %0, %1, %2, %3;" : "=r"(r) : "r"(gq), "r"(av), "r"(c)); return r; };
#pragma unroll
      for (int jj = 0; jj < 5; jj++) {
        const float* y0 = &y[8 * jj];
        stsm4(sa + jj * 32, mix(gg0, a[jj][0], pack2(y0[0], y0[1])), mix(gg1, a[jj][1], pack2(y0[2], y0[3])),
              mix(gg0, a[jj][2], pack2(y0[4], y0[5])), mix(gg1, a[jj][3], pack2(y0[6], y0[7])));
      }
      fence_async_s();
      __syncwarp();
      if (elect()) {
        tma2_store(&p.mout, tb, hg * 80, rb * 128 + warp * 16);
        bulk_commit();
        bulk_wait_read();
        mbar_arrive(B_DONE);
      }
    }
    if (tid == 0) TS(12);
  } else {
    asm volatile("setmaxnreg.inc.sync.aligned.u32 136;");
    const int stid = tid - 256, sw = warp - 8;
    {
      const float dsk = bflo(ldg16(p.dskip + 5 * b + sw));
#pragma unroll
      for (int c = 0; c < 5; c++) {
        float u[4], v[4];
        lds128f(u, A_TAB + (sw == 2 ? 29952 : (sw == 3 ? 16704 : 7168 * sw)) + c * 512 + lane * 16);
        lds128f(v, A_P4 + sw * 2560 + c * 512 + lane * 16);
        acc[c][0] += u[0] + v[0]; acc[c][1] += u[1] + v[1]; acc[c][2] += u[2] + v[2]; acc[c][3] += u[3] + v[3];
      }
      k0 += lds32f(A_DUM + 4 * sw) + lds32f(A_DUM + 16 + 4 * sw) + dsk;
      __syncwarp();
      uint32_t pe[4], po[2], px[4];
#pragma unroll
      for (int j = 0; j < 4; j++) { pe[j] = pack2(acc[j][0], acc[j][2]); px[j] = pack2(acc[j][1], acc[j][3]); }
      po[0] = pack2(acc[4][0], acc[4][2]); po[1] = pack2(acc[4][1], acc[4][3]);
      tables(A_TAB + sw * TABP, lane, pe, po, px, pack2(0.f, k0));
    }
    if (stid == 0) TS(21);
    mbar_wait(B_U, 0);
    if (stid == 0) TS(22);
    {
      float lo[24], hi[40];
      uint32_t A[CONV_SLOTS][4];
      uint32_t pa = A_TAB + 4 * (15 + 16 * sw + g - 2 * t);
      const uint32_t qa0 = A_PA + (lane >> 3) * 1024 + (8 * sw + ((7 - lane + sw) & 7)) * 16;
      const int half = (lane >> 3) & 1;
      const uint32_t so = A_PART + sw * 4096 + half * 2048 + (lane >> 4) * 128 + ((((lane & 7) + sw) ^ (4 * half)) << 4);
      const uint32_t sl = ((lane >> 4) && (lane & 7) + sw >= 8) ? A_DUM : so + 1792;
      uint64_t ud = desc(dlo(A_U + 768, UP / 2), 8), pd = desc(dlo(A_TAB + 4416, 288), 1);
      const int q = stid & 63, h = stid >> 6;
      uint32_t u0 = A_U + 768 - 16 + q * 16 + (h ? 0 : UP / 2 - 16), u1 = A_U + 768 - 16 + q * 16 + h * (UP / 2);
      const uint32_t da0 = A_PA + h * 1024 + (8 * (q & 7) + (((q >> 3) + q) & 7)) * 16;
#define PKH(T) stsm4t(T == 8 ? sl : so + 768 + T * 128, pack2(hi[4 * T], hi[4 * T + 1]), pack2(hi[4 * T + 2], hi[4 * T + 3]), pack2(hi[4 * T + 4], hi[4 * T + 5]), pack2(hi[4 * T + 6], hi[4 * T + 7]));
#define PKL(T) stsm4t(so + T * 128, pack2(lo[4 * T], lo[4 * T + 1]), pack2(lo[4 * T + 2], lo[4 * T + 3]), pack2(lo[4 * T + 4], lo[4 * T + 5]), pack2(lo[4 * T + 6], lo[4 * T + 7]));
      mbar_wait(B_TB, 0);
      lda4(A[2], pa + 4096);
      lda4(A[1], pa + 3840);
      lda4(A[6], pa + 3584);
      lda4(A[5], pa + 3328);
#pragma unroll 1
      for (int c = 0; c < 5; c++, pa += TABP, ud += UP >> 4, pd += TABP >> 4) {
        if (c == PG) bar_sync(7, 384);
        if (c == 0) {
#pragma unroll 1
          for (uint32_t da = da0; da != da0 + PG * 4096; u0 += UP, u1 += UP, da += 4096) {
            pool(u0, u1, da);
          }
          bar_sync(4, 128);
          if (stid == 0) TS(100 + c);
        }
        const uint32_t qa = qa0 + c * 4096 - (c < PG ? 0 : A_PA + PG * 4096 - A_PB), qb = qa ^ 576;
        wg_fence();
        wgmma_rs_n80(hi, A[2][0], A[2][1], A[2][2], A[2][3], ud - 16, 0);
        wgmma_rs_n80(hi, A[1][0], A[1][1], A[1][2], A[1][3], ud - 12, 1);
        wg_commit();
        wg_wait<2>();
        ldsm4t(A[3], qa);
        lda4(A[0], pa + 3072);
        wg_fence();
        wgmma_rs_n80(hi, A[6][0], A[6][1], A[6][2], A[6][3], ud - 8, 1);
        wgmma_rs_n80(hi, A[5][0], A[5][1], A[5][2], A[5][3], ud - 4, 1);
        wg_commit();
        wg_wait<2>();
        ldsm4t(A[9], qb);
        lda4(A[7], pa + 2816);
        wg_fence();
        wgmma_rs_n80(hi, A[0][0], A[0][1], A[0][2], A[0][3], ud + 0, 1);
        wgmma_rs_n80t(hi, A[3][0], A[3][1], A[3][2], A[3][3], pd + 0, 1);
        wg_commit();
        wg_wait<2>();
        lda4(A[8], pa + 2560);
        lda4(A[4], pa + 2304);
        wg_fence();
        wgmma_rs_n80t(hi, A[9][0], A[9][1], A[9][2], A[9][3], pd + 36, 1);
        wgmma_rs_n80(hi, A[7][0], A[7][1], A[7][2], A[7][3], ud + 4, 1);
        wg_commit();
        wg_wait<2>();
        lda4(A[5], pa + 2048);
        lda4(A[1], pa + 1792);
        wg_fence();
        wgmma_rs_n80(hi, A[8][0], A[8][1], A[8][2], A[8][3], ud + 8, 1);
        wgmma_rs_n80(hi, A[4][0], A[4][1], A[4][2], A[4][3], ud + 12, 1);
        wg_commit();
        wg_wait<2>();
        lda4(A[2], pa + 1536);
        wg_fence();
        wgmma_rs_n80(hi, A[5][0], A[5][1], A[5][2], A[5][3], ud + 16, 1);
        wgmma_rs_n80(hi, A[1][0], A[1][1], A[1][2], A[1][3], ud + 20, 1);
        wg_commit();
        wg_wait<2>();
        lda4(A[6], pa + 1280);
        wg_fence();
        wgmma_rs_n80(hi, A[2][0], A[2][1], A[2][2], A[2][3], ud + 24, 1);
        wgmma_rs_n48(lo, A[7][0], A[7][1], A[7][2], A[7][3], ud - 44, 0);
        wg_commit();
        wg_wait<2>();
        lda4(A[0], pa + 1024);
        wg_fence();
        wgmma_rs_n80(hi, A[6][0], A[6][1], A[6][2], A[6][3], ud + 28, 1);
        wgmma_rs_n48(lo, A[8][0], A[8][1], A[8][2], A[8][3], ud - 40, 1);
        wg_commit();
        wg_wait<2>();
        lda4(A[3], pa + 768);
        wg_fence();
        wgmma_rs_n80(hi, A[0][0], A[0][1], A[0][2], A[0][3], ud + 32, 1);
        wgmma_rs_n48(lo, A[4][0], A[4][1], A[4][2], A[4][3], ud - 36, 1);
        wg_commit();
        wg_wait<2>();
        lda4(A[7], pa + 512);
        wg_fence();
        wgmma_rs_n80(hi, A[3][0], A[3][1], A[3][2], A[3][3], ud + 36, 1);
        wgmma_rs_n48(lo, A[5][0], A[5][1], A[5][2], A[5][3], ud - 32, 1);
        wg_commit();
        wg_wait<2>();
        lda4(A[8], pa + 256);
        wg_fence();
        wgmma_rs_n80(hi, A[7][0], A[7][1], A[7][2], A[7][3], ud + 40, 1);
        wgmma_rs_n48(lo, A[1][0], A[1][1], A[1][2], A[1][3], ud - 28, 1);
        wg_commit();
        wg_wait<2>();
        lda4(A[4], pa + 0);
        wg_fence();
        wgmma_rs_n80(hi, A[8][0], A[8][1], A[8][2], A[8][3], ud + 44, 1);
        wgmma_rs_n48(lo, A[2][0], A[2][1], A[2][2], A[2][3], ud - 24, 1);
        wg_commit();
        wg_wait<2>();
        wg_fence();
        wgmma_rs_n80(hi, A[4][0], A[4][1], A[4][2], A[4][3], ud + 48, 1);
        wgmma_rs_n48(lo, A[6][0], A[6][1], A[6][2], A[6][3], ud - 20, 1);
        wg_commit();
        wg_wait<2>();
        wg_fence();
        wgmma_rs_n48(lo, A[0][0], A[0][1], A[0][2], A[0][3], ud - 16, 1);
        wgmma_rs_n48(lo, A[3][0], A[3][1], A[3][2], A[3][3], ud - 12, 1);
        wg_commit();
        wg_wait<1>();
        pin(hi);
        if (stid == 0) TS(40 + c);
        bar_sync(6, 192);
        if (stid == 0) TS(48 + c);
        PKH(0)
        wg_fence();
        wgmma_rs_n48(lo, A[7][0], A[7][1], A[7][2], A[7][3], ud - 8, 1);
        wg_commit();
        lda4(A[2], pa + TABP + 4096);
        lda4(A[1], pa + TABP + 3840);
        PKH(2)
        PKH(4)
        wg_fence();
        wgmma_rs_n48(lo, A[8][0], A[8][1], A[8][2], A[8][3], ud - 4, 1);
        wg_commit();
        lda4(A[6], pa + TABP + 3584);
        lda4(A[5], pa + TABP + 3328);
        PKH(6)
        PKH(8)
        wg_fence();
        wgmma_rs_n48(lo, A[4][0], A[4][1], A[4][2], A[4][3], ud - 0, 1);
        wg_commit();
        wg_wait<0>();
        pin(lo);
        if (c == TFC && elect()) mbar_arrive(B_TF);
        PKL(0)
        PKL(2)
        PKL(4)
        bar_arrive(5, 192);
        if (stid == 0) TS(32 + c);
      }
    }
    if (stid == 0) TS(13);
    {
      const int o = stid & 15, c0 = stid >> 4;
      const char* ga = g_s.aT + (80 * hg + c0) * 4096 + rb * 256 + o * 16;
      const uint32_t da = A_Q + (o >> 1) * 2560 + (((2 * c0 + ((o & 1) ^ ((c0 >> 2) & 1))) ^ (((o >> 1) & 3) << 1)) << 4);
      uint32_t X[10][4];
      int spin = 0; (void)spin;
      const uint32_t old = lds32(A_TAG);
      bar_sync(3, 192);
      mbar_wait(B_G, 0);
      poll_tag(g_s.aT + (80 * hg + 5 * o + 4) * 4096 + rb * 256 + 240, old);
      if (stid == 0) TS(38);
#pragma unroll
      for (int k = 0; k < 10; k++) ld_unit(X[k], ga + k * 32768);
      for (;;) {
        uint32_t m = 1;
#pragma unroll
        for (int k = 0; k < 10; k++) m &= X[k][0] ^ old;
        if (m) break;
        __nanosleep(NSLEEP);
#pragma unroll
        for (int k = 0; k < 10; k++) re_unit(X[k], ga + k * 32768, old);
        SPIN_GUARD(spin)
      }
      mbar_wait(B_C2, 0);
#pragma unroll
      for (int k = 0; k < 10; k++) sts128(da + 256 * k, X[k][0], X[k][1], X[k][2], X[k][3]);
      __syncwarp();
      if (elect()) mbar_arrive(B_AT);
    }
    if (stid == 0) TS(14);
  }
}

bool make_map(PFN_cuTensorMapEncodeTiled_v12000 enc, CUtensorMap* m, const void* base, int rank, const uint64_t* dims, const uint64_t* strides, const uint32_t* box, CUtensorMapSwizzle sw) {
  uint32_t es[5] = {1, 1, 1, 1, 1};
  return enc(m, CU_TENSOR_MAP_DATA_TYPE_BFLOAT16, rank, (void*)base, dims, strides, box, es, CU_TENSOR_MAP_INTERLEAVE_NONE, sw,
             CU_TENSOR_MAP_L2_PROMOTION_L2_128B, CU_TENSOR_MAP_FLOAT_OOB_FILL_NONE) == CUDA_SUCCESS;
}

}

extern "C" void kernel_launch(void* const* d_in, const int* in_sizes, int n_in, void* d_out, int out_size) {
  (void)in_sizes; (void)n_in; (void)out_size;
  void* fp = nullptr;
  cudaDriverEntryPointQueryResult qr;
  if (cudaGetDriverEntryPoint("cuTensorMapEncodeTiled", &fp, cudaEnableDefault, &qr) != cudaSuccess || !fp) return;
  PFN_cuTensorMapEncodeTiled_v12000 enc = (PFN_cuTensorMapEncodeTiled_v12000)fp;
  cudaFuncAttributes fa;
  if (cudaFuncGetAttributes(&fa, fused_kernel) != cudaSuccess || fa.numRegs != 128) return;
  Params p;
  p.x = (const bf16*)d_in[0]; p.Are = (const bf16*)d_in[1]; p.Aim = (const bf16*)d_in[2]; p.Bre = (const bf16*)d_in[3];
  p.Bim = (const bf16*)d_in[4]; p.Cre = (const bf16*)d_in[5]; p.Cim = (const bf16*)d_in[6]; p.logdt = (const bf16*)d_in[7];
  p.dskip = (const bf16*)d_in[8]; p.gatew = (const bf16*)d_in[12];
  bool ok = true;
  {
    uint64_t d[2] = {640, 2048}, s[1] = {1280};
    uint32_t bx[2] = {64, 128}, bo[2] = {80, 16}, bs[2] = {80, 128};
    ok &= make_map(enc, &p.mx, d_in[0], 2, d, s, bx, CU_TENSOR_MAP_SWIZZLE_128B);
    ok &= make_map(enc, &p.mxs, d_in[0], 2, d, s, bs, CU_TENSOR_MAP_SWIZZLE_NONE);
    ok &= make_map(enc, &p.mout, d_out, 2, d, s, bo, CU_TENSOR_MAP_SWIZZLE_NONE);
  }
  {
    uint64_t d[3] = {640, 640, 3}, s[2] = {3840, 1280};
    uint32_t b64[3] = {64, 64, 3}, b16[3] = {16, 64, 3};
    ok &= make_map(enc, &p.mw64, d_in[10], 3, d, s, b64, CU_TENSOR_MAP_SWIZZLE_128B);
    ok &= make_map(enc, &p.mw16, d_in[10], 3, d, s, b16, CU_TENSOR_MAP_SWIZZLE_32B);
  }
  {
    uint64_t d[3] = {16, 640, 40}, s[2] = {1280, 32};
    uint32_t bx[3] = {16, 80, 5};
    ok &= make_map(enc, &p.mwo, d_in[11], 3, d, s, bx, CU_TENSOR_MAP_SWIZZLE_32B);
  }
  {
    void* gs = nullptr;
    if (cudaGetSymbolAddress(&gs, g_s) != cudaSuccess) return;
    uint64_t d[3] = {UP / 4, 2, 640}, s[2] = {UP / 2, UP};
    uint32_t bx[3] = {64, 2, UBX};
    ok &= make_map(enc, &p.mut, gs, 3, d, s, bx, CU_TENSOR_MAP_SWIZZLE_128B);
  }
  if (!ok) return;
  cudaFuncSetAttribute(fused_kernel, cudaFuncAttributeMaxDynamicSharedMemorySize, (int)SMEM_BYTES);
  fused_kernel<<<128, 512, SMEM_BYTES, cudaStreamPerThread>>>(p);
}
```
